```python
import torch

def _softmax(x, axis=-1):
    return torch.softmax(x, dim=axis)
def _gelu(x):
    return torch.nn.functional.gelu(x, approximate="tanh")
def _silu(x):
    return torch.nn.functional.silu(x)
def _sigmoid(x):
    return torch.sigmoid(x)
def _layernorm(x, axis=-1, eps=1e-5):
    m = x.mean(dim=axis, keepdim=True)
    v = x.var(dim=axis, keepdim=True, unbiased=False)
    return (x - m) / torch.sqrt(v + eps)
def _scatter_add(tgt, idx, src, axis=0):
    return tgt.clone().index_add_(axis, idx, src)
def _segment_sum(src, seg, n):
    out = torch.zeros((n,) + src.shape[1:], dtype=src.dtype)
    return out.index_add_(0, seg, src)
def _pad(x, pw):
    flat = tuple(v for pair in reversed(pw) for v in pair)
    return torch.nn.functional.pad(x, flat)

kernel_name = 'sequential_preLN__gqa_block_cached__glu_gated_geglu__decode'

def setup_inputs():

    _w = (lambda a: (lambda t: t.to(torch.bfloat16) if t.is_floating_point() else t)(torch.as_tensor(a)))
    def _A_setup():
        B, Sq, D = 4, 1, 512
        Hq, Hkv, Sk, Dh = 32, 8, 4096, 128
        assert Hq % Hkv == 0, (Hq, Hkv)
        return {
            "x": _w((lambda *s: torch.randn(*s, dtype=torch.bfloat16) * 0.05)(B, Sq, D)),
            "k_cache": _w((lambda *s: torch.randn(*s, dtype=torch.bfloat16) * 1.6)(B, Hkv, Sk, Dh)),
            "v_cache": _w((lambda *s: torch.randn(*s, dtype=torch.bfloat16) * 0.8)(B, Hkv, Sk, Dh)),
            "wq": _w((lambda *s: torch.randn(*s, dtype=torch.bfloat16) * 1.6)(D, Hq * Dh) * (D ** -0.5)),
            "wo": _w((lambda *s: torch.randn(*s, dtype=torch.bfloat16) * 0.8)(Hq * Dh, D) * ((Hq * Dh) ** -0.5)),
        }
    _A_in = _A_setup()

    def _B_setup():
        B, S, Dm, Df = 4, 1, 512, 1792
        return {
            "x": _w((lambda *s: torch.randn(*s, dtype=torch.bfloat16) * 0.05)(B, S, Dm)),
            "w_gate": _w((lambda *s: torch.randn(*s, dtype=torch.bfloat16) * 0.8)(Dm, Df) * (Dm ** -0.5)),
            "w_up": _w((lambda *s: torch.randn(*s, dtype=torch.bfloat16) * 0.8)(Dm, Df) * (Dm ** -0.5)),
            "w_down": _w((lambda *s: torch.randn(*s, dtype=torch.bfloat16) * 0.8)(Df, Dm) * (Df ** -0.5)),
        }
    _B_in = _B_setup()

    return {
        "A_x": _A_in["x"],
        "A_k_cache": _A_in["k_cache"],
        "A_v_cache": _A_in["v_cache"],
        "A_wq": _A_in["wq"],
        "A_wo": _A_in["wo"],
        "B_x": _B_in["x"],
        "B_w_gate": _B_in["w_gate"],
        "B_w_up": _B_in["w_up"],
        "B_w_down": _B_in["w_down"],
    }

def reference(A_x, A_k_cache, A_v_cache, A_wq, A_wo, B_x, B_w_gate, B_w_up, B_w_down):
    def _A_ref(x, k_cache, v_cache, wq, wo):
        B, Sq, D = x.shape
        Hq, Dh = 32, 128
        Hkv = k_cache.shape[1]
        rep = Hq // Hkv
        q = (lambda x, *d: x.permute(*d))((x @ wq).reshape(B, Sq, Hq, Dh), 0, 2, 1, 3)
        k = (lambda x, n, axis: torch.repeat_interleave(x, n, dim=axis))(k_cache, rep, axis=1)
        v = (lambda x, n, axis: torch.repeat_interleave(x, n, dim=axis))(v_cache, rep, axis=1)
        scores = torch.einsum("bhqd,bhkd->bhqk", q, k) * (Dh ** -0.5)
        p = _softmax(scores, axis=-1)
        o = torch.einsum("bhqk,bhkd->bhqd", p, v)
        return (lambda x, *d: x.permute(*d))(o, 0, 2, 1, 3).reshape(B, Sq, Hq * Dh) @ wo

    def _B_ref(x, w_gate, w_up, w_down):
        g = torch.einsum("bsd,df->bsf", x, w_gate)
        u = torch.einsum("bsd,df->bsf", x, w_up)
        h = _gelu(g) * u
        return torch.einsum("bsf,fd->bsd", h, w_down)

    x = A_x
    h = x + _A_ref(_layernorm(x, axis=-1), A_k_cache, A_v_cache, A_wq, A_wo)
    h2 = h + _B_ref(_layernorm(h, axis=-1), B_w_gate, B_w_up, B_w_down)
    return h2
```

```cpp
#include <cuda_runtime.h>
#include <cuda_bf16.h>
#include <cuda.h>
#include <stdint.h>
#include <stdio.h>
#include <cooperative_groups.h>
namespace cg = cooperative_groups;

#define NSTAGE 12
#define STAGE_BYTES 16384
#define NCTA 128
#define NKV 32
#define NTOT 37

__device__ __align__(16) float g_attn[4 * 512];
__device__ __align__(16) float g_ffn[4 * 512];
__device__ unsigned int g_bar[4];
__device__ __align__(16) __nv_bfloat16 g_q[4 * 4096];
__device__ float g_part[128][520];
__device__ unsigned int g_done;

__device__ __forceinline__ uint32_t s2u(const void* p) { return (uint32_t)__cvta_generic_to_shared(p); }
__device__ __forceinline__ void mbar_init(uint32_t a, uint32_t c) { asm volatile("mbarrier.init.shared::cta.b64 [%0], %1;" :: "r"(a), "r"(c)); }
__device__ __forceinline__ void mbar_expect(uint32_t a, uint32_t b) { asm volatile("mbarrier.arrive.expect_tx.shared::cta.b64 _, [%0], %1;" :: "r"(a), "r"(b) : "memory"); }
__device__ __forceinline__ void mbar_arrive(uint32_t a) { asm volatile("mbarrier.arrive.shared::cta.b64 _, [%0];" :: "r"(a) : "memory"); }
__device__ __forceinline__ void mbar_wait(uint32_t a, uint32_t par) {
    uint32_t ok = 0;
    for (int it = 0; it < (1 << 22) && !ok; it++)
        asm volatile("{.reg .pred p; mbarrier.try_wait.parity.shared::cta.b64 p, [%1], %2; selp.u32 %0,1,0,p;}" : "=r"(ok) : "r"(a), "r"(par) : "memory");
}
__device__ __forceinline__ void tma2d(uint32_t dst, const CUtensorMap* m, int c0, int c1, uint32_t bar) {
    asm volatile("cp.async.bulk.tensor.2d.shared::cluster.global.mbarrier::complete_tx::bytes [%0], [%1, {%3, %4}], [%2];"
        :: "r"(dst), "l"((uint64_t)m), "r"(bar), "r"(c0), "r"(c1) : "memory");
}
__device__ __forceinline__ void bulk1d(uint32_t dst, const void* src, uint32_t bytes, uint32_t bar) {
    asm volatile("cp.async.bulk.shared::cluster.global.mbarrier::complete_tx::bytes [%0], [%1], %2, [%3];"
        :: "r"(dst), "l"(src), "r"(bytes), "r"(bar) : "memory");
}
__device__ __forceinline__ void ldsm4(uint32_t a, uint32_t& r0, uint32_t& r1, uint32_t& r2, uint32_t& r3) {
    asm volatile("ldmatrix.sync.aligned.m8n8.x4.shared.b16 {%0,%1,%2,%3}, [%4];" : "=r"(r0), "=r"(r1), "=r"(r2), "=r"(r3) : "r"(a));
}
__device__ __forceinline__ void ldsm4t(uint32_t a, uint32_t& r0, uint32_t& r1, uint32_t& r2, uint32_t& r3) {
    asm volatile("ldmatrix.sync.aligned.m8n8.x4.trans.shared.b16 {%0,%1,%2,%3}, [%4];" : "=r"(r0), "=r"(r1), "=r"(r2), "=r"(r3) : "r"(a));
}
__device__ __forceinline__ void mma(float* c, uint32_t a0, uint32_t a1, uint32_t a2, uint32_t a3, uint32_t b0, uint32_t b1) {
    asm volatile("mma.sync.aligned.m16n8k16.row.col.f32.bf16.bf16.f32 {%0,%1,%2,%3}, {%4,%5,%6,%7}, {%8,%9}, {%0,%1,%2,%3};"
        : "+f"(c[0]), "+f"(c[1]), "+f"(c[2]), "+f"(c[3]) : "r"(a0), "r"(a1), "r"(a2), "r"(a3), "r"(b0), "r"(b1));
}
__device__ __forceinline__ uint32_t pack2(float a, float b) { __nv_bfloat162 v = __floats2bfloat162_rn(a, b); return *(uint32_t*)&v; }
__device__ __forceinline__ float bfr(float a) { return __bfloat162float(__float2bfloat16(a)); }
__device__ __forceinline__ void cbar() { asm volatile("bar.sync 1, 256;" ::: "memory"); }

#define TS(i)
struct Smem {
    alignas(1024) unsigned char ring[NSTAGE][STAGE_BYTES];
    float comb[8][520];
    float lnv[4][512];
    float hv[4][512];
    __nv_bfloat16 q[4][128];
    float red[64];
    unsigned long long full[NSTAGE], empty[NSTAGE];
    unsigned int flag;
};

__device__ __forceinline__ void ln512(float v0, float v1, float* red, float* dst, int tid) {
    float s = v0 + v1;
    for (int o = 16; o; o >>= 1) s += __shfl_xor_sync(~0u, s, o);
    if ((tid & 31) == 0) red[tid >> 5] = s;
    cbar();
    float m = 0; for (int i = 0; i < 8; i++) m += red[i];
    m *= (1.f / 512.f);
    float d0 = v0 - m, d1 = v1 - m;
    float q = d0 * d0 + d1 * d1;
    for (int o = 16; o; o >>= 1) q += __shfl_xor_sync(~0u, q, o);
    if ((tid & 31) == 0) red[8 + (tid >> 5)] = q;
    cbar();
    float var = 0; for (int i = 0; i < 8; i++) var += red[8 + i];
    float rs = rsqrtf(var * (1.f / 512.f) + 1e-5f);
    dst[2 * tid] = bfr(d0 * rs); dst[2 * tid + 1] = bfr(d1 * rs);
    cbar();
}

__device__ __forceinline__ void ln4(const float* v, float* red, float (*dst)[512], int tid) {
    float s = 0, q = 0;
    #pragma unroll
    for (int i = 0; i < 8; i++) { s += v[i]; q += v[i] * v[i]; }
    for (int o = 16; o; o >>= 1) { s += __shfl_xor_sync(~0u, s, o); q += __shfl_xor_sync(~0u, q, o); }
    if ((tid & 31) == 0) { red[tid >> 5] = s; }
    cbar();
    float m = (red[(tid >> 6) * 2] + red[(tid >> 6) * 2 + 1]) * (1.f / 512.f);
    q = 0;
    #pragma unroll
    for (int i = 0; i < 8; i++) q += (v[i] - m) * (v[i] - m);
    for (int o = 16; o; o >>= 1) q += __shfl_xor_sync(~0u, q, o);
    if ((tid & 31) == 0) red[8 + (tid >> 5)] = q;
    cbar();
    float rs = rsqrtf((red[8 + (tid >> 6) * 2] + red[8 + (tid >> 6) * 2 + 1]) * (1.f / 512.f) + 1e-5f);
    #pragma unroll
    for (int i = 0; i < 8; i++) dst[tid >> 6][(tid & 63) * 8 + i] = bfr((v[i] - m) * rs);
    cbar();
}
__device__ __forceinline__ void red4(float* base, const float* a0, const float* a1, int tid) {
    bool ev = !(tid & 1);
    float s0 = ev ? a0[2] : a0[0], s1 = ev ? a1[2] : a1[0], s2 = ev ? a0[3] : a0[1], s3 = ev ? a1[3] : a1[1];
    s0 = __shfl_xor_sync(~0u, s0, 1); s1 = __shfl_xor_sync(~0u, s1, 1); s2 = __shfl_xor_sync(~0u, s2, 1); s3 = __shfl_xor_sync(~0u, s3, 1);
    int c = (tid & ~1) * 2, bb = ev ? 0 : 2;
    float v[2][4];
    if (ev) { v[0][0] = a0[0]; v[0][1] = a1[0]; v[0][2] = s0; v[0][3] = s1; v[1][0] = a0[1]; v[1][1] = a1[1]; v[1][2] = s2; v[1][3] = s3; }
    else    { v[0][0] = s0; v[0][1] = s1; v[0][2] = a0[2]; v[0][3] = a1[2]; v[1][0] = s2; v[1][1] = s3; v[1][2] = a0[3]; v[1][3] = a1[3]; }
    #pragma unroll
    for (int i = 0; i < 2; i++)
        asm volatile("red.global.add.v4.f32 [%0], {%1,%2,%3,%4};" :: "l"(base + (bb + i) * 512 + c), "f"(v[i][0]), "f"(v[i][1]), "f"(v[i][2]), "f"(v[i][3]) : "memory");
}
__device__ __forceinline__ void gridbar(int i, int tid) {
    __threadfence();
    cbar();
    if (tid == 0) {
        atomicAdd(&g_bar[i], 1u);
        unsigned v = 0;
        for (int it = 0; it < (1 << 22); it++) { asm volatile("ld.acquire.gpu.global.u32 %0, [%1];" : "=r"(v) : "l"(&g_bar[i]) : "memory"); if (v >= NCTA) break; }
    }
    cbar();
}

__global__ void __launch_bounds__(288, 1)
fused_kernel(const __grid_constant__ CUtensorMap tmK, const __grid_constant__ CUtensorMap tmV,
             const __grid_constant__ CUtensorMap tmG, const __grid_constant__ CUtensorMap tmU,
             const __nv_bfloat16* __restrict__ x, const __nv_bfloat16* __restrict__ wq,
             const __nv_bfloat16* __restrict__ wo, const __nv_bfloat16* __restrict__ wd,
             __nv_bfloat16* __restrict__ out)
{
    extern __shared__ __align__(1024) unsigned char smraw[];
    Smem& S = *(Smem*)smraw;
    const int tid = threadIdx.x, warp = tid >> 5, lane = tid & 31;
    const int cta = blockIdx.x, rank = cta & 3, grp = cta >> 2;
    const int b = grp >> 3, hkv = grp & 7, head = hkv * 4 + rank;

    if (tid == 0) {
        for (int i = 0; i < NSTAGE; i++) { mbar_init(s2u(&S.full[i]), 1); mbar_init(s2u(&S.empty[i]), 4); }
        asm volatile("fence.mbarrier_init.release.cluster;" ::: "memory");
    }
    __syncthreads();

    if (warp == 8) {
        const int row0 = grp * 4096 + rank * 1024;
        auto issue = [&](int i) {
            int st = i % NSTAGE; uint32_t fb = s2u(&S.full[st]); uint32_t dst = s2u(S.ring[st]);
            mbar_wait(s2u(&S.empty[st]), ((i / NSTAGE) & 1) ^ 1);
            mbar_expect(fb, STAGE_BYTES);
            if (i < NKV) {
                const CUtensorMap* m = (i & 1) ? &tmV : &tmK;
                int r = row0 + (i >> 1) * 64;
                tma2d(dst, m, 0, r, fb); tma2d(dst + 8192, m, 64, r, fb);
            } else if (i < NKV + 2) {
                bulk1d(dst, wo + (size_t)(cta * 32 + (i - NKV) * 16) * 512, STAGE_BYTES, fb);
            } else {
                int c = cta < 112 ? cta : 111;
                if (i == NKV + 4) bulk1d(dst, wd + (size_t)c * 16 * 512, STAGE_BYTES, fb);
                else { const CUtensorMap* m = (i == NKV + 2) ? &tmG : &tmU;
                       tma2d(dst, m, c * 16, 0, fb); tma2d(dst + 8192, m, c * 16, 256, fb); }
            }
        };
        asm volatile("bar.sync 2, 288;" ::: "memory");
        if (lane == 0) for (int i = 0; i < 5; i++) issue(i);
        asm volatile("bar.sync 2, 288;" ::: "memory");
        if (lane == 0) for (int i = 5; i < NTOT; i++) issue(i);
        return;
    }

    TS(0);
    {
        const int cgp = tid & 3, rg = tid >> 2;
        float acc[4][8];
        #pragma unroll
        for (int i = 0; i < 4; i++) for (int j = 0; j < 8; j++) acc[i][j] = 0.f;
        const __nv_bfloat16* wp = wq + (size_t)(rg * 8) * 4096 + cta * 32 + cgp * 8;
        uint4 w[8];
        #pragma unroll
        for (int i = 0; i < 8; i++) w[i] = __ldg((const uint4*)(wp + (size_t)i * 4096));
        {
            uint4 xv = *(const uint4*)(x + tid * 8); float v[8];
            const __nv_bfloat162* xp = (const __nv_bfloat162*)&xv;
            #pragma unroll
            for (int j = 0; j < 4; j++) { float2 f = __bfloat1622float2(xp[j]); v[2 * j] = f.x; v[2 * j + 1] = f.y; }
            ln4(v, S.red, S.lnv, tid);
        }
        asm volatile("" :: "r"(w[7].x), "r"(w[0].x), "r"(w[3].x));
        asm volatile("bar.sync 2, 288;" ::: "memory");
        #pragma unroll
        for (int i = 0; i < 8; i++) {
            const __nv_bfloat162* p = (const __nv_bfloat162*)&w[i];
            #pragma unroll
            for (int bb = 0; bb < 4; bb++) {
                float a = S.lnv[bb][rg * 8 + i];
                #pragma unroll
                for (int j = 0; j < 4; j++) { float2 f = __bfloat1622float2(p[j]); acc[bb][2 * j] += a * f.x; acc[bb][2 * j + 1] += a * f.y; }
            }
        }
        #pragma unroll
        for (int bb = 0; bb < 4; bb++)
            #pragma unroll
            for (int j = 0; j < 8; j++) {
                float v = acc[bb][j];
                v += __shfl_xor_sync(~0u, v, 4); v += __shfl_xor_sync(~0u, v, 8); v += __shfl_xor_sync(~0u, v, 16);
                acc[bb][j] = v;
            }
        float* rb = &S.comb[0][0];
        if (lane < 4) {
            #pragma unroll
            for (int bb = 0; bb < 4; bb++)
                #pragma unroll
                for (int j = 0; j < 8; j++) rb[warp * 128 + bb * 32 + lane * 8 + j] = acc[bb][j];
        }
        cbar();
        if (tid < 128) {
            float sum = 0;
            #pragma unroll
            for (int i = 0; i < 8; i++) sum += rb[i * 128 + tid];
            g_q[(tid >> 5) * 4096 + cta * 32 + (tid & 31)] = __float2bfloat16(sum);
        }
        gridbar(0, tid);
        asm volatile("bar.sync 2, 288;" ::: "memory");
        if (tid < 64) ((uint4*)&S.q[0][0])[tid] = __ldcg((const uint4*)&g_q[b * 4096 + hkv * 512] + tid);
        cbar();
    }

    TS(1);
    const int g = lane >> 2, t = lane & 3;
    uint32_t qa[8][2];
    #pragma unroll
    for (int k = 0; k < 8; k++) {
        qa[k][0] = g < 4 ? *(const uint32_t*)&S.q[g][k * 16 + 2 * t] : 0u;
        qa[k][1] = g < 4 ? *(const uint32_t*)&S.q[g][k * 16 + 8 + 2 * t] : 0u;
    }
    float o[16][4];
    #pragma unroll
    for (int i = 0; i < 16; i++) { o[i][0] = o[i][1] = o[i][2] = o[i][3] = 0.f; }
    float mrun = -INFINITY, lrun = 0.f;
    const float sc = 0.08838834764831845f * 1.4426950408889634f;
    #pragma unroll 1
    const int wq4 = warp & 3;
    for (int tp = warp >> 2; tp < 16; tp += 2) {
        int ik = 2 * tp, iv = 2 * tp + 1;
        uint32_t kb = s2u(S.ring[ik % NSTAGE]), vb = s2u(S.ring[iv % NSTAGE]);
        mbar_wait(s2u(&S.full[ik % NSTAGE]), (ik / NSTAGE) & 1);
        float s[2][4];
        #pragma unroll
        for (int n = 0; n < 2; n++) {
            s[n][0] = s[n][1] = s[n][2] = s[n][3] = 0.f;
            int r = wq4 * 16 + n * 8 + (lane & 7);
            #pragma unroll
            for (int kk = 0; kk < 4; kk++) {
                int ch = (kk & 1) * 4 + (lane >> 3);
                uint32_t a = kb + (kk >> 1) * 8192 + r * 128 + ((ch ^ (r & 7)) << 4);
                uint32_t b0, b1, b2, b3; ldsm4(a, b0, b1, b2, b3);
                mma(s[n], qa[2 * kk][0], 0, qa[2 * kk][1], 0, b0, b1);
                mma(s[n], qa[2 * kk + 1][0], 0, qa[2 * kk + 1][1], 0, b2, b3);
            }
        }
        __syncwarp();
        if (lane == 0) mbar_arrive(s2u(&S.empty[ik % NSTAGE]));
        float mx = fmaxf(mrun, fmaxf(fmaxf(s[0][0], s[0][1]), fmaxf(s[1][0], s[1][1])));
        mx = fmaxf(mx, __shfl_xor_sync(~0u, mx, 1)); mx = fmaxf(mx, __shfl_xor_sync(~0u, mx, 2));
        float corr = exp2f((mrun - mx) * sc);
        mrun = mx;
        float p0 = exp2f((s[0][0] - mx) * sc), p1 = exp2f((s[0][1] - mx) * sc);
        float p2 = exp2f((s[1][0] - mx) * sc), p3 = exp2f((s[1][1] - mx) * sc);
        uint32_t pa0 = pack2(p0, p1), pa1 = pack2(p2, p3);
        lrun = lrun * corr + (p0 + p1 + p2 + p3);
        #pragma unroll
        for (int i = 0; i < 16; i++) { o[i][0] *= corr; o[i][1] *= corr; }
        mbar_wait(s2u(&S.full[iv % NSTAGE]), (iv / NSTAGE) & 1);
        {
            int r = wq4 * 16 + (lane & 15);
            #pragma unroll
            for (int n2 = 0; n2 < 8; n2++) {
                int ch = (n2 & 3) * 2 + (lane >> 4);
                uint32_t a = vb + (n2 >> 2) * 8192 + r * 128 + ((ch ^ (r & 7)) << 4);
                uint32_t b0, b1, b2, b3; ldsm4t(a, b0, b1, b2, b3);
                mma(o[2 * n2], pa0, 0, pa1, 0, b0, b1);
                mma(o[2 * n2 + 1], pa0, 0, pa1, 0, b2, b3);
            }
        }
        __syncwarp();
        if (lane == 0) mbar_arrive(s2u(&S.empty[iv % NSTAGE]));
    }
    TS(2);
    lrun += __shfl_xor_sync(~0u, lrun, 1); lrun += __shfl_xor_sync(~0u, lrun, 2);
    if (g < 4) {
        #pragma unroll
        for (int i = 0; i < 16; i++) { S.comb[warp][g * 128 + i * 8 + 2 * t] = o[i][0]; S.comb[warp][g * 128 + i * 8 + 2 * t + 1] = o[i][1]; }
        if (t == 0) { S.comb[warp][512 + g] = mrun; S.comb[warp][516 + g] = lrun; }
    }
    cbar();
    #pragma unroll
    for (int j = tid; j < 512; j += 256) {
        int h = j >> 7;
        float M = -INFINITY;
        #pragma unroll
        for (int w = 0; w < 8; w++) M = fmaxf(M, S.comb[w][512 + h]);
        float acc = 0, L = 0;
        #pragma unroll
        for (int w = 0; w < 8; w++) { float e = exp2f((S.comb[w][512 + h] - M) * sc); acc += e * S.comb[w][j]; L += e * S.comb[w][516 + h]; }
        g_part[cta][j] = acc;
        if ((j & 127) == 0) { g_part[cta][512 + h] = M; g_part[cta][516 + h] = L; }
    }
    gridbar(1, tid);
    TS(3);
    {
        float* ov = &S.comb[0][0];
        if (tid < 128) {
            int bb = tid >> 5, d = cta * 32 + (tid & 31);
            int hh = d >> 7, c0 = (bb * 8 + (hh >> 2)) * 4, hl = hh & 3, dl = hl * 128 + (d & 127);
            float m[4], e, L = 0, acc = 0;
            #pragma unroll
            for (int r = 0; r < 4; r++) m[r] = __ldcg(&g_part[c0 + r][512 + hl]);
            float M = fmaxf(fmaxf(m[0], m[1]), fmaxf(m[2], m[3]));
            #pragma unroll
            for (int r = 0; r < 4; r++) { e = exp2f((m[r] - M) * sc); L += e * __ldcg(&g_part[c0 + r][516 + hl]); acc += e * __ldcg(&g_part[c0 + r][dl]); }
            ov[tid] = bfr(acc / L);
        }
        cbar();
        float a0[4] = {0, 0, 0, 0}, a1[4] = {0, 0, 0, 0};
        #pragma unroll
        for (int st = 0; st < 2; st++) {
            int i = NKV + st;
            mbar_wait(s2u(&S.full[i % NSTAGE]), (i / NSTAGE) & 1);
            const __nv_bfloat162* wp = (const __nv_bfloat162*)S.ring[i % NSTAGE] + tid;
            #pragma unroll
            for (int r = 0; r < 16; r++) {
                float2 f = __bfloat1622float2(wp[r * 256]);
                #pragma unroll
                for (int bb = 0; bb < 4; bb++) { float a = ov[bb * 32 + st * 16 + r]; a0[bb] += a * f.x; a1[bb] += a * f.y; }
            }
        }
        red4(g_attn, a0, a1, tid);
    }
    TS(4);
    gridbar(2, tid);
    TS(5);
    {
        uint4 xv = *(const uint4*)(x + tid * 8); float v[8];
        float4 a0 = __ldcg((const float4*)&g_attn[tid * 8]), a1 = __ldcg((const float4*)&g_attn[tid * 8 + 4]);
        float av[8] = {a0.x, a0.y, a0.z, a0.w, a1.x, a1.y, a1.z, a1.w};
        const __nv_bfloat162* xp = (const __nv_bfloat162*)&xv;
        #pragma unroll
        for (int j = 0; j < 4; j++) { float2 f = __bfloat1622float2(xp[j]); v[2 * j] = bfr(f.x + bfr(av[2 * j])); v[2 * j + 1] = bfr(f.y + bfr(av[2 * j + 1])); }
        #pragma unroll
        for (int j = 0; j < 8; j++) S.hv[tid >> 6][(tid & 63) * 8 + j] = v[j];
        ln4(v, S.red, S.lnv, tid);
    }
    if (cta < 112) {
        const int ig = NKV + 2, iu = NKV + 3, id = NKV + 4;
        mbar_wait(s2u(&S.full[ig % NSTAGE]), (ig / NSTAGE) & 1);
        mbar_wait(s2u(&S.full[iu % NSTAGE]), (iu / NSTAGE) & 1);
        const __nv_bfloat16* G = (const __nv_bfloat16*)S.ring[ig % NSTAGE];
        const __nv_bfloat16* U = (const __nv_bfloat16*)S.ring[iu % NSTAGE];
        const int c = tid & 15, rg = tid >> 4;
        float ga[4] = {0, 0, 0, 0}, ua[4] = {0, 0, 0, 0};
        #pragma unroll 8
        for (int i = 0; i < 32; i++) {
            int r = rg * 32 + i;
            float gw = __bfloat162float(G[r * 16 + c]), uw = __bfloat162float(U[r * 16 + c]);
            #pragma unroll
            for (int bb = 0; bb < 4; bb++) { float a = S.lnv[bb][r]; ga[bb] += a * gw; ua[bb] += a * uw; }
        }
        float* rb = &S.comb[0][0];
        #pragma unroll
        for (int bb = 0; bb < 4; bb++) { rb[(rg * 8 + bb) * 16 + c] = ga[bb]; rb[(rg * 8 + 4 + bb) * 16 + c] = ua[bb]; }
        cbar();
        float* hm = &S.comb[6][0];
        if (tid < 64) {
            int bb = tid >> 4; float gs = 0, us = 0;
            #pragma unroll
            for (int i = 0; i < 16; i++) { gs += rb[(i * 8 + bb) * 16 + c]; us += rb[(i * 8 + 4 + bb) * 16 + c]; }
            gs = bfr(gs); us = bfr(us);
            float ge = 0.5f * gs * (1.f + tanhf(0.7978845608028654f * (gs + 0.044715f * gs * gs * gs)));
            hm[tid] = bfr(bfr(ge) * us);
        }
        cbar();
        mbar_wait(s2u(&S.full[id % NSTAGE]), (id / NSTAGE) & 1);
        const __nv_bfloat162* D = (const __nv_bfloat162*)S.ring[id % NSTAGE] + tid;
        float d0[4] = {0, 0, 0, 0}, d1[4] = {0, 0, 0, 0};
        #pragma unroll
        for (int r = 0; r < 16; r++) {
            float2 f = __bfloat1622float2(D[r * 256]);
            #pragma unroll
            for (int bb = 0; bb < 4; bb++) { float a = hm[bb * 16 + r]; d0[bb] += a * f.x; d1[bb] += a * f.y; }
        }
        red4(g_ffn, d0, d1, tid);
    } else {
        for (int i = NKV + 2; i < NTOT; i++) mbar_wait(s2u(&S.full[i % NSTAGE]), (i / NSTAGE) & 1);
    }
    __threadfence();
    cbar();
    TS(6);
    if (tid == 0) S.flag = atomicAdd(&g_done, 1u);
    cbar();
    if (S.flag == NCTA - 1) {
        __threadfence();
        #pragma unroll
        for (int bb = 0; bb < 4; bb++) {
            float2 f = __ldcg((const float2*)&g_ffn[bb * 512 + 2 * tid]);
            out[bb * 512 + 2 * tid] = __float2bfloat16(S.hv[bb][2 * tid] + bfr(f.x));
            out[bb * 512 + 2 * tid + 1] = __float2bfloat16(S.hv[bb][2 * tid + 1] + bfr(f.y));
            *(float2*)&g_ffn[bb * 512 + 2 * tid] = make_float2(0.f, 0.f);
            *(float2*)&g_attn[bb * 512 + 2 * tid] = make_float2(0.f, 0.f);
        }
        if (tid < 3) g_bar[tid] = 0; if (tid == 0) g_done = 0;
    }
}

typedef CUresult (*EncFn)(CUtensorMap*, CUtensorMapDataType, cuuint32_t, void*, const cuuint64_t*, const cuuint64_t*, const cuuint32_t*, const cuuint32_t*, CUtensorMapInterleave, CUtensorMapSwizzle, CUtensorMapL2promotion, CUtensorMapFloatOOBfill);

static void mk(EncFn f, CUtensorMap* m, void* p, uint64_t cols, uint64_t rows, uint32_t bc, uint32_t br, CUtensorMapSwizzle sw) {
    cuuint64_t dim[2] = {cols, rows}, str[1] = {cols * 2}; cuuint32_t box[2] = {bc, br}, es[2] = {1, 1};
    f(m, CU_TENSOR_MAP_DATA_TYPE_BFLOAT16, 2, p, dim, str, box, es, CU_TENSOR_MAP_INTERLEAVE_NONE, sw, CU_TENSOR_MAP_L2_PROMOTION_L2_256B, CU_TENSOR_MAP_FLOAT_OOB_FILL_NONE);
}

extern "C" void kernel_launch(void* const* d_in, const int* in_sizes, int n_in, void* d_out, int out_size) {
    static EncFn f = nullptr;
    if (!f) {
        cudaDriverEntryPointQueryResult qr;
        cudaGetDriverEntryPoint("cuTensorMapEncodeTiled", (void**)&f, cudaEnableDefault, &qr);
        cudaFuncSetAttribute(fused_kernel, cudaFuncAttributeMaxDynamicSharedMemorySize, (int)sizeof(Smem));
    }
    CUtensorMap tk, tv, tg, tu;
    mk(f, &tk, d_in[1], 128, 131072, 64, 64, CU_TENSOR_MAP_SWIZZLE_128B);
    mk(f, &tv, d_in[2], 128, 131072, 64, 64, CU_TENSOR_MAP_SWIZZLE_128B);
    mk(f, &tg, d_in[6], 1792, 512, 16, 256, CU_TENSOR_MAP_SWIZZLE_NONE);
    mk(f, &tu, d_in[7], 1792, 512, 16, 256, CU_TENSOR_MAP_SWIZZLE_NONE);
    fused_kernel<<<NCTA, 288, sizeof(Smem)>>>(tk, tv, tg, tu, (const __nv_bfloat16*)d_in[0], (const __nv_bfloat16*)d_in[3],
        (const __nv_bfloat16*)d_in[4], (const __nv_bfloat16*)d_in[8], (__nv_bfloat16*)d_out);
}
```
